```python
import torch

def _softmax(x, axis=-1):
    return torch.softmax(x, dim=axis)
def _gelu(x):
    return torch.nn.functional.gelu(x, approximate="tanh")
def _silu(x):
    return torch.nn.functional.silu(x)
def _sigmoid(x):
    return torch.sigmoid(x)
def _layernorm(x, axis=-1, eps=1e-5):
    m = x.mean(dim=axis, keepdim=True)
    v = x.var(dim=axis, keepdim=True, unbiased=False)
    return (x - m) / torch.sqrt(v + eps)
def _scatter_add(tgt, idx, src, axis=0):
    return tgt.clone().index_add_(axis, idx, src)
def _segment_sum(src, seg, n):
    out = torch.zeros((n,) + src.shape[1:], dtype=src.dtype)
    return out.index_add_(0, seg, src)
def _pad(x, pw):
    flat = tuple(v for pair in reversed(pw) for v in pair)
    return torch.nn.functional.pad(x, flat)

kernel_name = 'standalone__sliding_block_cached__sampling'

def setup_inputs():

    _w = (lambda a: (lambda t: t.to(torch.bfloat16) if t.is_floating_point() else t)(torch.as_tensor(a)))
    B, Sq, D = 8, 32, 512
    Hq, Hkv, Sk, Dh = 32, 8, 8192, 128
    assert Hq % Hkv == 0, (Hq, Hkv)
    return {
        "x": _w((lambda *s: torch.randn(*s, dtype=torch.bfloat16) * 0.8)(B, Sq, D)),
        "k_cache": _w((lambda *s: torch.randn(*s, dtype=torch.bfloat16) * 0.8)(B, Hkv, Sk, Dh)),
        "v_cache": _w((lambda *s: torch.randn(*s, dtype=torch.bfloat16) * 0.05)(B, Hkv, Sk, Dh)),
        "wq": _w((lambda *s: torch.randn(*s, dtype=torch.bfloat16) * 0.8)(D, Hq * Dh) * (D ** -0.5)),
        "wo": _w((lambda *s: torch.randn(*s, dtype=torch.bfloat16) * 0.05)(Hq * Dh, D) * ((Hq * Dh) ** -0.5)),
    }

def reference(x, k_cache, v_cache, wq, wo):
    B, Sq, D = x.shape
    Hq, Dh = 32, 128
    Hkv, Sk = k_cache.shape[1], k_cache.shape[2]
    W = min(4096, max(256, Sk // 4))
    rep = Hq // Hkv
    q = (lambda x, *d: x.permute(*d))((x @ wq).reshape(B, Sq, Hq, Dh), 0, 2, 1, 3)
    k = (lambda x, n, axis: torch.repeat_interleave(x, n, dim=axis))(k_cache[:, :, Sk - W:, :], rep, axis=1)
    v = (lambda x, n, axis: torch.repeat_interleave(x, n, dim=axis))(v_cache[:, :, Sk - W:, :], rep, axis=1)
    scores = torch.einsum("bhqd,bhkd->bhqk", q, k) * (Dh ** -0.5)
    p = _softmax(scores, axis=-1)
    o = torch.einsum("bhqk,bhkd->bhqd", p, v)
    return (lambda x, *d: x.permute(*d))(o, 0, 2, 1, 3).reshape(B, Sq, Hq * Dh) @ wo
```

```cpp
#include <cuda_runtime.h>
#include <cuda_bf16.h>
#include <cuda.h>
#include <stdint.h>

namespace {

constexpr int kB = 8, kSq = 32, kD = 512, kHq = 32, kHkv = 8, kSk = 8192, kDh = 128, kW = 2048;
constexpr int kSlots = 7;
constexpr uint32_t kSlotBytes = 32768;
constexpr uint32_t kHalfBytes = 16384;
constexpr int kThreads = 384;
constexpr int kCtas = 128;
constexpr uint32_t kBarOff = kSlots * kSlotBytes;
constexpr uint32_t kMlOff = kBarOff + 512;
constexpr uint32_t kSmemBytes = kMlOff + 2048;
constexpr int kNumTiles = 36;
constexpr int kBarFull = 0;
constexpr int kBarEmpty = 36;
constexpr int kBarXw = 43;
constexpr int kBarQFree = 49;
constexpr int kBarQReady = 50;
constexpr int kBarOFree = 51;
constexpr int kBarOReady = 52;
constexpr int kBarMbox = 56;
constexpr int kNumBars = 57;
constexpr int kSlotWq0 = 6, kSlotWq1 = 1, kSlotXa = 2, kSlotWq2 = 3, kSlotWq3 = 4, kSlotXb = 5;
constexpr int kSlotQ = kSlotWq0;
constexpr int kSlotDump = 1;
constexpr int kSlotO = 0;
#define INFLIGHT 2
constexpr int kInFlight = INFLIGHT;
#define PFMODE 0
#define PF_T0 0
#define PF_N 3
#define PF_OFF 0
constexpr uint32_t kSpinLimit = 1u << 20;

__device__ uint4 g_box[16 * 16 * 16 * 64];
__device__ unsigned int g_cleared[4 * 32];

#define TRACE(who, idx)

__device__ __forceinline__ uint32_t smem_u32(const void* p) { return (uint32_t)__cvta_generic_to_shared(p); }
__device__ __forceinline__ void mbar_init(uint32_t bar, uint32_t cnt) {
    asm volatile("mbarrier.init.shared::cta.b64 [%0], %1;" ::"r"(bar), "r"(cnt));
}
__device__ __forceinline__ void mbar_expect_tx(uint32_t bar, uint32_t bytes) {
    asm volatile("mbarrier.arrive.expect_tx.shared::cta.b64 _, [%0], %1;" ::"r"(bar), "r"(bytes) : "memory");
}
__device__ __forceinline__ void mbar_arrive_n(uint32_t bar, uint32_t n) {
    asm volatile("mbarrier.arrive.shared::cta.b64 _, [%0], %1;" ::"r"(bar), "r"(n) : "memory");
}
__device__ __forceinline__ bool mbar_try(uint32_t bar, uint32_t parity) {
    uint32_t ok;
    asm volatile(
        "{\n.reg .pred p;\nmbarrier.try_wait.parity.shared::cta.b64 p, [%1], %2;\nselp.b32 %0, 1, 0, p;\n}"
        : "=r"(ok)
        : "r"(bar), "r"(parity)
        : "memory");
    return ok;
}
__device__ __forceinline__ void mbar_wait(uint32_t bar, uint32_t parity) {
    uint32_t it = 0;
    while (!mbar_try(bar, parity)) {
        if (++it > kSpinLimit) break;
    }
}
__device__ __forceinline__ void tma_2d(uint32_t dst, const CUtensorMap* map, int c0, int c1, uint32_t bar) {
    asm volatile(
        "cp.async.bulk.tensor.2d.shared::cluster.global.mbarrier::complete_tx::bytes [%0], [%1, {%3, %4}], [%2];" ::"r"(dst),
        "l"(map), "r"(bar), "r"(c0), "r"(c1)
        : "memory");
}
__device__ __forceinline__ void tma_2d_hint(uint32_t dst, const CUtensorMap* map, int c0, int c1, uint32_t bar, uint64_t pol) {
    asm volatile(
        "cp.async.bulk.tensor.2d.shared::cluster.global.mbarrier::complete_tx::bytes.L2::cache_hint [%0], [%1, {%3, %4}], [%2], %5;" ::"r"(dst),
        "l"(map), "r"(bar), "r"(c0), "r"(c1), "l"(pol)
        : "memory");
}
__device__ __forceinline__ uint32_t mapa(uint32_t addr, uint32_t rank) {
    uint32_t r;
    asm volatile("mapa.shared::cluster.u32 %0, %1, %2;" : "=r"(r) : "r"(addr), "r"(rank));
    return r;
}
__device__ __forceinline__ void mbar_arrive_remote(uint32_t cluster_addr) {
    asm volatile("mbarrier.arrive.shared::cluster.b64 _, [%0];" ::"r"(cluster_addr) : "memory");
}
__device__ __forceinline__ void st_async16(uint32_t cluster_addr, uint32_t w0, uint32_t w1, uint32_t w2, uint32_t w3, uint32_t cluster_bar) {
    asm volatile("st.async.weak.shared::cluster.mbarrier::complete_tx::bytes.v4.b32 [%0], {%1, %2, %3, %4}, [%5];" ::"r"(cluster_addr),
                 "r"(w0), "r"(w1), "r"(w2), "r"(w3), "r"(cluster_bar)
                 : "memory");
}
__device__ __forceinline__ void st_shared16(uint32_t addr, uint32_t w0, uint32_t w1, uint32_t w2, uint32_t w3) {
    asm volatile("st.shared.v4.b32 [%0], {%1, %2, %3, %4};" ::"r"(addr), "r"(w0), "r"(w1), "r"(w2), "r"(w3) : "memory");
}
__device__ __forceinline__ void ld_shared16(uint32_t addr, uint32_t& w0, uint32_t& w1, uint32_t& w2, uint32_t& w3) {
    asm volatile("ld.shared.v4.b32 {%0, %1, %2, %3}, [%4];" : "=r"(w0), "=r"(w1), "=r"(w2), "=r"(w3) : "r"(addr) : "memory");
}
__device__ __forceinline__ void cluster_arrive() { asm volatile("barrier.cluster.arrive.relaxed.aligned;" ::: "memory"); }
__device__ __forceinline__ void cluster_wait() { asm volatile("barrier.cluster.wait.acquire.aligned;" ::: "memory"); }
__device__ __forceinline__ void bar_sync(int id, int n) { asm volatile("bar.sync %0, %1;" ::"r"(id), "r"(n) : "memory"); }
__device__ __forceinline__ void bar_arrive(int id, int n) { asm volatile("bar.arrive %0, %1;" ::"r"(id), "r"(n) : "memory"); }

__device__ __forceinline__ uint32_t pack_bf16(float lo, float hi) {
    uint32_t r;
    asm("cvt.rn.bf16x2.f32 %0, %1, %2;" : "=r"(r) : "f"(hi), "f"(lo));
    return r;
}
__device__ __forceinline__ float ex2(float x) {
    float y;
    asm("ex2.approx.ftz.f32 %0, %1;" : "=f"(y) : "f"(x));
    return y;
}
__device__ __forceinline__ float bf_lo(uint32_t w) { return __uint_as_float(w << 16); }
__device__ __forceinline__ float bf_hi(uint32_t w) { return __uint_as_float(w & 0xffff0000u); }

__device__ __forceinline__ void st_chunk(uint4* p, uint32_t w0, uint32_t w1, uint32_t w2, uint32_t w3) {
    w0 = (w0 == 0u) ? 0x80000000u : w0;
    asm volatile(
        "{\n.reg .b128 v;\n.reg .b64 lo, hi;\nmov.b64 lo, {%1, %2};\nmov.b64 hi, {%3, %4};\nmov.b128 v, {lo, hi};\n"
        "st.relaxed.gpu.global.b128 [%0], v;\n}" ::"l"(p),
        "r"(w0), "r"(w1), "r"(w2), "r"(w3)
        : "memory");
}
__device__ __forceinline__ void ld_chunk(const uint4* p, uint32_t& w0, uint32_t& w1, uint32_t& w2, uint32_t& w3) {
    asm volatile(
        "{\n.reg .b128 v;\n.reg .b64 lo, hi;\nld.relaxed.gpu.global.b128 v, [%4];\nmov.b128 {lo, hi}, v;\n"
        "mov.b64 {%0, %1}, lo;\nmov.b64 {%2, %3}, hi;\n}"
        : "=r"(w0), "=r"(w1), "=r"(w2), "=r"(w3)
        : "l"(p)
        : "memory");
}

__device__ __forceinline__ uint64_t make_desc(uint32_t addr, uint32_t lbo_bytes, uint32_t sbo_bytes) {
    return (uint64_t)((addr & 0x3FFFFu) >> 4) | ((uint64_t)(lbo_bytes >> 4) << 16) | ((uint64_t)(sbo_bytes >> 4) << 32) |
           (1ull << 62);
}
__device__ __forceinline__ void wg_fence() { asm volatile("wgmma.fence.sync.aligned;" ::: "memory"); }
__device__ __forceinline__ void wg_commit() { asm volatile("wgmma.commit_group.sync.aligned;" ::: "memory"); }
template <int N>
__device__ __forceinline__ void wg_wait() {
    asm volatile("wgmma.wait_group.sync.aligned %0;" ::"n"(N) : "memory");
}
template <int N>
__device__ __forceinline__ void fence_regs(float (&r)[N]) {
#pragma unroll
    for (int i = 0; i < N; i++) asm volatile("" : "+f"(r[i])::"memory");
}
template <int N>
__device__ __forceinline__ void fence_regs(uint32_t (&r)[N]) {
#pragma unroll
    for (int i = 0; i < N; i++) asm volatile("" : "+r"(r[i])::"memory");
}

#define ACC8(d, o) "+f"(d[o + 0]), "+f"(d[o + 1]), "+f"(d[o + 2]), "+f"(d[o + 3]), "+f"(d[o + 4]), "+f"(d[o + 5]), "+f"(d[o + 6]), "+f"(d[o + 7])

template <int TRANS_B>
__device__ __forceinline__ void wgmma_rs_n128(float (&d)[64], uint32_t a0, uint32_t a1, uint32_t a2, uint32_t a3, uint64_t descB,
                                              int scale_d) {
    asm volatile(
        "{\n.reg .pred p;\nsetp.ne.b32 p, %69, 0;\n"
        "wgmma.mma_async.sync.aligned.m64n128k16.f32.bf16.bf16 "
        "{%0, %1, %2, %3, %4, %5, %6, %7, %8, %9, %10, %11, %12, %13, %14, %15, "
        "%16, %17, %18, %19, %20, %21, %22, %23, %24, %25, %26, %27, %28, %29, %30, %31, "
        "%32, %33, %34, %35, %36, %37, %38, %39, %40, %41, %42, %43, %44, %45, %46, %47, "
        "%48, %49, %50, %51, %52, %53, %54, %55, %56, %57, %58, %59, %60, %61, %62, %63}, "
        "{%64, %65, %66, %67}, %68, p, 1, 1, %70;\n}"
        : ACC8(d, 0), ACC8(d, 8), ACC8(d, 16), ACC8(d, 24), ACC8(d, 32), ACC8(d, 40), ACC8(d, 48), ACC8(d, 56)
        : "r"(a0), "r"(a1), "r"(a2), "r"(a3), "l"(descB), "r"(scale_d), "n"(TRANS_B));
}
__device__ __forceinline__ void wgmma_rs_n64(float (&d)[32], uint32_t a0, uint32_t a1, uint32_t a2, uint32_t a3, uint64_t descB,
                                             int scale_d) {
    asm volatile(
        "{\n.reg .pred p;\nsetp.ne.b32 p, %37, 0;\n"
        "wgmma.mma_async.sync.aligned.m64n64k16.f32.bf16.bf16 "
        "{%0, %1, %2, %3, %4, %5, %6, %7, %8, %9, %10, %11, %12, %13, %14, %15, "
        "%16, %17, %18, %19, %20, %21, %22, %23, %24, %25, %26, %27, %28, %29, %30, %31}, "
        "{%32, %33, %34, %35}, %36, p, 1, 1, 1;\n}"
        : ACC8(d, 0), ACC8(d, 8), ACC8(d, 16), ACC8(d, 24)
        : "r"(a0), "r"(a1), "r"(a2), "r"(a3), "l"(descB), "r"(scale_d));
}
__device__ __forceinline__ void wgmma_ss_n64(float (&d)[32], uint64_t descA, uint64_t descB, int scale_d) {
    asm volatile(
        "{\n.reg .pred p;\nsetp.ne.b32 p, %34, 0;\n"
        "wgmma.mma_async.sync.aligned.m64n64k16.f32.bf16.bf16 "
        "{%0, %1, %2, %3, %4, %5, %6, %7, %8, %9, %10, %11, %12, %13, %14, %15, "
        "%16, %17, %18, %19, %20, %21, %22, %23, %24, %25, %26, %27, %28, %29, %30, %31}, "
        "%32, %33, p, 1, 1, 0, 1;\n}"
        : ACC8(d, 0), ACC8(d, 8), ACC8(d, 16), ACC8(d, 24)
        : "l"(descA), "l"(descB), "r"(scale_d));
}

__device__ __forceinline__ int tile_slot(int t) { return t < 25 ? t % kSlots : (t < 32 ? (t - 25) & 3 : (t == 35 ? 3 : t - 28)); }

struct alignas(64) Params {
    CUtensorMap k, v, wo, wq, x;
};

__global__ void __launch_bounds__(kThreads, 1)
fused_swa_kernel(const __grid_constant__ Params prm, const __nv_bfloat16* __restrict__ kptr, const __nv_bfloat16* __restrict__ vptr,
                 __nv_bfloat16* __restrict__ out) {
    extern __shared__ __align__(1024) uint8_t smem[];
    const uint32_t sbase = smem_u32(smem);
    const uint32_t bars = sbase + kBarOff;
    auto bar = [&](int i) { return bars + 8 * i; };

    const int tid = threadIdx.x;
    const int warp = __shfl_sync(0xffffffffu, tid >> 5, 0), lane = tid & 31;
    const int cta = blockIdx.x;
    const int r = cta & 1;
    int pc, s;
    {
        const int c = cta >> 1;
        if (c < 4) {
            pc = c >> 1, s = c & 1;
        } else if (c < 36) {
            const int u = c - 4;
            pc = 2 + (u >> 4) * 8 + (u & 7), s = (u >> 3) & 1;
        } else {
            const int u = c - 36, hi = u >= 14, v = u - 14 * hi;
            s = v >= 7;
            pc = 18 + 7 * hi + v - 7 * s;
        }
    }
    const int bp = pc >> 3, hkv = pc & 7;
    const int b = 2 * bp + r;
    const int head0 = 4 * hkv + 2 * s;

    if (warp >= 8) {
        asm volatile("setmaxnreg.dec.sync.aligned.u32 40;");
        const int kv_row0 = (b * kHkv + hkv) * kSk + (kSk - kW);
        if (warp == 8) {
            if (lane == 0) {
#pragma unroll
                for (int i = 0; i < 6; i++) mbar_init(bar(kBarXw + i), 1);
                mbar_init(bar(kBarFull), 1);
                asm volatile("fence.mbarrier_init.release.cluster;" ::: "memory");
            }
            __syncwarp();
            cluster_arrive();
            uint64_t pol_stream;
            asm volatile("createpolicy.fractional.L2::evict_first.b64 %0, 1.0;" : "=l"(pol_stream));
            if (lane == 0) {
                TRACE(2, 0);
                auto load_x = [&](int half, int slot) {
                    const uint32_t fb = bar(kBarXw + 4 + half), dst = sbase + slot * kSlotBytes;
                    mbar_expect_tx(fb, kSlotBytes);
#pragma unroll
                    for (int i = 0; i < 4; i++) tma_2d(dst + i * 8192, &prm.x, 256 * half + 64 * i, 64 * bp, fb);
                };
                auto load_wq = [&](int chunk, int slot) {
                    const uint32_t fb = bar(kBarXw + chunk), dst = sbase + slot * kSlotBytes;
                    mbar_expect_tx(fb, kSlotBytes);
                    tma_2d(dst, &prm.wq, (head0 + r) * 128, 128 * chunk, fb);
                    tma_2d(dst + kHalfBytes, &prm.wq, (head0 + r) * 128 + 64, 128 * chunk, fb);
                };
                auto pf = [&](int i) {
                };
                load_wq(0, kSlotWq0);
                load_x(0, kSlotXa);
                pf(0 - PF_OFF);
                load_wq(1, kSlotWq1);
                pf(1 - PF_OFF);
                load_x(1, kSlotXb);
                load_wq(2, kSlotWq2);
                pf(2 - PF_OFF);
                load_wq(3, kSlotWq3);
                pf(3 - PF_OFF);
                TRACE(2, 40);
#define K0_WAIT -1
                if (K0_WAIT >= 0) mbar_wait(bar(kBarXw + K0_WAIT), 0);
                mbar_expect_tx(bar(kBarFull), kSlotBytes);
                tma_2d_hint(sbase, &prm.k, 0, kv_row0, bar(kBarFull), pol_stream);
                tma_2d_hint(sbase + kHalfBytes, &prm.k, 64, kv_row0, bar(kBarFull), pol_stream);
                TRACE(2, 1);
            }
            __syncwarp();
            cluster_wait();
            if (lane == 0) {
                uint32_t phase = 0;
                int prev1 = 0, prev2 = -1;
#pragma unroll 1
                for (int n = 1; n < kNumTiles; n++) {
                    int t;
                    if (n < 22) t = n;
                    else if (n == 22) t = 32;
                    else if (n < 25) t = n - 1;
                    else if (n == 25) t = 33;
                    else if (n < 28) t = n - 2;
                    else if (n == 28) t = 34;
                    else if (n < 34) t = n - 3;
                    else t = n == 34 ? 35 : 31;
                    const int slot = tile_slot(t);
                    mbar_wait(bar(kBarEmpty + slot), (phase >> slot) & 1);
                    phase ^= 1u << slot;
#define DEEP_T 99
#define DEEP_D 3
                    const int depth = t >= DEEP_T ? DEEP_D : kInFlight;
                    if (t >= depth && t < 32) mbar_wait(bar(kBarFull + t - depth), 0);
                    const uint32_t fb = bar(kBarFull + t), dst = sbase + slot * kSlotBytes;
                    mbar_expect_tx(fb, kSlotBytes);
                    if (t < 32) {
                        const CUtensorMap* m = (t < 28 ? (t & 1) : (t >> 1 & 1)) ? &prm.v : &prm.k;
                        const int row = kv_row0 + (t < 28 ? t >> 1 : 14 + (t & 1)) * 128;
                        tma_2d_hint(dst, m, 0, row, fb, pol_stream);
                        tma_2d_hint(dst + kHalfBytes, m, 64, row, fb, pol_stream);
                    } else {
                        const int row = (head0 + ((t - 32) >> 1)) * 128, col = 256 * r + 128 * (t & 1);
                        tma_2d(dst, &prm.wo, col, row, fb);
                        tma_2d(dst + kHalfBytes, &prm.wo, col + 64, row, fb);
                    }
                    TRACE(2, 1 + t);
                }
            }
        } else {
            if (warp == 9 && lane == 0) {
                asm volatile("prefetch.tensormap [%0];" ::"l"(&prm.wq) : "memory");
                asm volatile("prefetch.tensormap [%0];" ::"l"(&prm.x) : "memory");
                asm volatile("prefetch.tensormap [%0];" ::"l"(&prm.k) : "memory");
                asm volatile("prefetch.tensormap [%0];" ::"l"(&prm.v) : "memory");
                asm volatile("prefetch.tensormap [%0];" ::"l"(&prm.wo) : "memory");
#pragma unroll
                for (int i = 1; i < kNumTiles; i++) mbar_init(bar(kBarFull + i), 1);
                asm volatile("fence.mbarrier_init.release.cluster;" ::: "memory");
            }
            if (warp == 10 && lane == 0) {
#pragma unroll
                for (int i = 0; i < kSlots; i++) mbar_init(bar(kBarEmpty + i), 8);
                mbar_init(bar(kBarQFree), 16);
                mbar_init(bar(kBarQReady), 5);
                mbar_init(bar(kBarOFree), 4);
#pragma unroll
                for (int i = 0; i < 4; i++) mbar_init(bar(kBarOReady + i), 5);
                mbar_init(bar(kBarMbox), 1);
                mbar_expect_tx(bar(kBarQReady), 8192);
#pragma unroll
                for (int i = 0; i < 4; i++) mbar_expect_tx(bar(kBarOReady + i), 4096);
                asm volatile("fence.mbarrier_init.release.cluster;" ::: "memory");
            }
            __syncwarp();
            cluster_arrive();
            cluster_wait();
            if (warp == 9) {
            } else {
#define CLR_T 4
#define CLR_PER 2
                uint4* z = g_box + ((size_t)(bp * 4 + 2 * r) * 16 * 16 + 2 * hkv + s) * 64 + (tid & 63);
#pragma unroll 1
                for (int i = 0; i < 32; i += CLR_PER) {
                    if (i > 0)
                    mbar_wait(bar(kBarFull + CLR_T + i / CLR_PER), 0);
#pragma unroll
                    for (int u = 0; u < CLR_PER; u++) z[(i + u) * 16 * 64] = make_uint4(0, 0, 0, 0);
                }
                __threadfence();
                bar_sync(4, 64);
                if (warp == 10 && lane == 0) {
                    unsigned int* cnt = &g_cleared[bp * 32];
                    const unsigned int target = (atomicAdd(cnt, 1u) & ~31u) + 32u;
                    uint32_t it = 0;
                    while (true) {
                        unsigned int v;
                        asm volatile("ld.acquire.gpu.global.u32 %0, [%1];" : "=r"(v) : "l"(cnt) : "memory");
                        if ((int)(v - target) >= 0 || ++it > kSpinLimit) break;
                        __nanosleep(200);
                    }
                    mbar_arrive_n(bar(kBarMbox), 1);
                }
            }
        }
        return;
    }

    asm volatile("setmaxnreg.inc.sync.aligned.u32 232;");
    const int g = warp >> 2;
    const int w = warp & 3;
    const int wtid = tid & 127;
    const bool tr = (wtid == 0);
    (void)tr;
    if (tr) TRACE(g, 0);
    cluster_arrive();
    cluster_wait();

    {
        float acc[32];
#pragma unroll
        for (int c = 0; c < 4; c++) {
            const int slotW = c == 0 ? kSlotWq0 : (c == 1 ? kSlotWq1 : (c == 2 ? kSlotWq2 : kSlotWq3));
            const int slotX = c < 2 ? kSlotXa : kSlotXb;
            if ((c & 1) == 0) mbar_wait(bar(kBarXw + 4 + (c >> 1)), 0);
            mbar_wait(bar(kBarXw + c), 0);
            if (tr) TRACE(g, 22 + c);
            wg_fence();
            const uint32_t wb = sbase + slotW * kSlotBytes + g * kHalfBytes;
            const uint32_t xb = sbase + slotX * kSlotBytes + (c & 1) * kHalfBytes;
#pragma unroll
            for (int kk = 0; kk < 8; kk++)
                wgmma_ss_n64(acc, make_desc(xb + (kk >> 2) * 8192 + (kk & 3) * 32, 16, 1024), make_desc(wb + kk * 2048, kHalfBytes, 1024),
                             (c | kk) != 0);
            wg_commit();
            wg_wait<0>();
            fence_regs(acc);
            if (lane == 0) {
                if (c == 0) {
                    mbar_arrive_remote(mapa(bar(kBarQFree), 0));
                    mbar_arrive_remote(mapa(bar(kBarQFree), 1));
                } else {
                    mbar_arrive_n(bar(kBarEmpty + slotW), 1);
                    if (c & 1) mbar_arrive_n(bar(kBarEmpty + slotX), 1);
                }
            }
        }
        if (tr) TRACE(g, 1);
        mbar_wait(bar(kBarQFree), 0);
        const uint32_t dst = sbase + kSlotQ * kSlotBytes + (((r * 2 + (w & 1)) * 8 + 4 * g) * 32 + lane) * 16;
        if ((w >> 1) == r) {
#pragma unroll
            for (int t = 0; t < 4; t++)
                st_shared16(dst + t * 512, pack_bf16(acc[8 * t], acc[8 * t + 1]), pack_bf16(acc[8 * t + 2], acc[8 * t + 3]),
                            pack_bf16(acc[8 * t + 4], acc[8 * t + 5]), pack_bf16(acc[8 * t + 6], acc[8 * t + 7]));
            __syncwarp();
            if (lane == 0) mbar_arrive_n(bar(kBarQReady), 1);
        } else {
            const uint32_t rdst = mapa(dst, r ^ 1), rbar = mapa(bar(kBarQReady), r ^ 1);
#pragma unroll
            for (int t = 0; t < 4; t++)
                st_async16(rdst + t * 512, pack_bf16(acc[8 * t], acc[8 * t + 1]), pack_bf16(acc[8 * t + 2], acc[8 * t + 3]),
                           pack_bf16(acc[8 * t + 4], acc[8 * t + 5]), pack_bf16(acc[8 * t + 6], acc[8 * t + 7]), rbar);
        }
        if (tr) TRACE(g, 2);
    }

    uint32_t q[32];
    {
        mbar_wait(bar(kBarQReady), 0);
        const uint32_t src = sbase + kSlotQ * kSlotBytes + (w * 8 * 32 + lane) * 16;
#pragma unroll
        for (int t = 0; t < 8; t++) ld_shared16(src + t * 512, q[4 * t], q[4 * t + 1], q[4 * t + 2], q[4 * t + 3]);
        fence_regs(q);
        __syncwarp();
        if (lane == 0) mbar_arrive_n(bar(kBarEmpty + kSlotQ), 1);
    }
    if (tr) TRACE(g, 3);

    const float sc = 0.08838834764831845f * 1.4426950408889634f;
    float o[64];
#pragma unroll
    for (int i = 0; i < 64; i++) o[i] = 0.f;
    float m0 = -INFINITY, m1 = -INFINITY, l0 = 0.f, l1 = 0.f;

    auto attn_tile = [&](int tK, int tV, uint32_t (&pf)[32]) {
        const int sK = tile_slot(tK), sV = tile_slot(tV);
        float sacc[64];
        mbar_wait(bar(kBarFull + tK), 0);
        fence_regs(q);
        wg_fence();
        {
            const uint32_t kb = sbase + sK * kSlotBytes;
#pragma unroll
            for (int kk = 0; kk < 8; kk++) {
                const uint64_t db = make_desc(kb + (kk >> 2) * kHalfBytes + (kk & 3) * 32, 16, 1024);
                wgmma_rs_n128<0>(sacc, q[4 * kk], q[4 * kk + 1], q[4 * kk + 2], q[4 * kk + 3], db, kk != 0);
            }
        }
        wg_commit();
        wg_wait<0>();
        fence_regs(sacc);
        if (lane == 0) {
            if (tK != 29) mbar_arrive_n(bar(kBarEmpty + sK), 2);
            else mbar_arrive_remote(mapa(bar(kBarOFree), r ^ 1));
        }

        float x0 = sacc[0], x1 = sacc[2];
#pragma unroll
        for (int j = 0; j < 16; j++) {
            x0 = fmaxf(x0, fmaxf(sacc[4 * j], sacc[4 * j + 1]));
            x1 = fmaxf(x1, fmaxf(sacc[4 * j + 2], sacc[4 * j + 3]));
        }
        x0 = fmaxf(x0, __shfl_xor_sync(0xffffffffu, x0, 1));
        x1 = fmaxf(x1, __shfl_xor_sync(0xffffffffu, x1, 1));
        x0 = fmaxf(x0, __shfl_xor_sync(0xffffffffu, x0, 2));
        x1 = fmaxf(x1, __shfl_xor_sync(0xffffffffu, x1, 2));
        const float n0 = fmaxf(m0, x0), n1 = fmaxf(m1, x1);
        const float c0 = ex2((m0 - n0) * sc), c1 = ex2((m1 - n1) * sc);
        m0 = n0;
        m1 = n1;
        const float ms0 = n0 * sc, ms1 = n1 * sc;
        float r0 = 0.f, r1 = 0.f;
#pragma unroll
        for (int j = 0; j < 16; j++) {
            const float p0 = ex2(fmaf(sacc[4 * j], sc, -ms0));
            const float p1 = ex2(fmaf(sacc[4 * j + 1], sc, -ms0));
            const float p2 = ex2(fmaf(sacc[4 * j + 2], sc, -ms1));
            const float p3 = ex2(fmaf(sacc[4 * j + 3], sc, -ms1));
            r0 += p0 + p1;
            r1 += p2 + p3;
            pf[2 * j] = pack_bf16(p0, p1);
            pf[2 * j + 1] = pack_bf16(p2, p3);
        }
        l0 = l0 * c0 + r0;
        l1 = l1 * c1 + r1;
#pragma unroll
        for (int j = 0; j < 16; j++) {
            o[4 * j] *= c0;
            o[4 * j + 1] *= c0;
            o[4 * j + 2] *= c1;
            o[4 * j + 3] *= c1;
        }
        mbar_wait(bar(kBarFull + tV), 0);
        if (tr && tV >= 30) TRACE(g, 4);
        fence_regs(o);
        fence_regs(pf);
        wg_fence();
        {
            const uint32_t vb = sbase + sV * kSlotBytes;
#pragma unroll
            for (int kk = 0; kk < 8; kk++) {
                const uint64_t db = make_desc(vb + kk * 2048, kHalfBytes, 1024);
                wgmma_rs_n128<1>(o, pf[4 * kk], pf[4 * kk + 1], pf[4 * kk + 2], pf[4 * kk + 3], db, 1);
            }
        }
        wg_commit();
    };

#pragma unroll 1
    for (int i = 0; i < 8 - g; i++) {
        const int tK = i < 7 ? 4 * i + 2 * g : 28, tV = i < 7 ? tK + 1 : 30;
        uint32_t pf[32];
        attn_tile(tK, tV, pf);
        wg_wait<0>();
        fence_regs(o);
        if (lane == 0 && tV < 28) mbar_arrive_n(bar(kBarEmpty + tile_slot(tV)), 2);
        if (tr && i < 7) TRACE(g, 8 + i);
    }

    if (g == 0) {
        if (tr) TRACE(g, 5);
        bar_sync(1, 128);
        float4* dump = reinterpret_cast<float4*>(smem + kSlotDump * kSlotBytes);
#pragma unroll
        for (int j = 0; j < 16; j++) dump[j * 128 + wtid] = make_float4(o[4 * j], o[4 * j + 1], o[4 * j + 2], o[4 * j + 3]);
        *reinterpret_cast<float4*>(smem + kMlOff + wtid * 16) = make_float4(m0, m1, l0, l1);
        bar_arrive(3, 256);
    } else {
        uint32_t pf[32];
        attn_tile(29, 31, pf);
        if (tr) TRACE(g, 26);
        bar_sync(3, 256);
        const float4 ml = *reinterpret_cast<const float4*>(smem + kMlOff + wtid * 16);
        const float n0 = fmaxf(m0, ml.x), n1 = fmaxf(m1, ml.y);
        const float e0 = ex2((ml.x - n0) * sc), e1 = ex2((ml.y - n1) * sc);
        const float c0 = ex2((m0 - n0) * sc), c1 = ex2((m1 - n1) * sc);
        float t0 = fmaf(ml.z, e0, l0 * c0), t1 = fmaf(ml.w, e1, l1 * c1);
        t0 += __shfl_xor_sync(0xffffffffu, t0, 1);
        t1 += __shfl_xor_sync(0xffffffffu, t1, 1);
        t0 += __shfl_xor_sync(0xffffffffu, t0, 2);
        t1 += __shfl_xor_sync(0xffffffffu, t1, 2);
        const float inv0 = 1.f / t0, inv1 = 1.f / t1;
        const float a0 = c0 * inv0, a1 = c1 * inv1, b0 = e0 * inv0, b1 = e1 * inv1;
        float y[64];
        const float4* dump = reinterpret_cast<const float4*>(smem + kSlotDump * kSlotBytes);
#pragma unroll
        for (int j = 0; j < 16; j++) {
            const float4 v = dump[j * 128 + wtid];
            y[4 * j] = v.x * b0, y[4 * j + 1] = v.y * b0, y[4 * j + 2] = v.z * b1, y[4 * j + 3] = v.w * b1;
        }
        fence_regs(y);
        if (tr) TRACE(g, 27);
        mbar_wait(bar(kBarOFree), 0);
        wg_wait<0>();
        fence_regs(o);
        if (tr) TRACE(g, 5);
        const uint32_t dst = sbase + kSlotO * kSlotBytes + ((((2 * r + (w & 1)) * 2 + (w >> 1)) * 8) * 32 + lane) * 16;
        const uint32_t rdst = mapa(dst, r ^ 1), rbar = mapa(bar(kBarOReady), r ^ 1);
#pragma unroll
        for (int t = 0; t < 8; t++) {
            const int x = 8 * t;
            const uint32_t w0 = pack_bf16(fmaf(o[x], a0, y[x]), fmaf(o[x + 1], a0, y[x + 1]));
            const uint32_t w1 = pack_bf16(fmaf(o[x + 2], a1, y[x + 2]), fmaf(o[x + 3], a1, y[x + 3]));
            const uint32_t w2 = pack_bf16(fmaf(o[x + 4], a0, y[x + 4]), fmaf(o[x + 5], a0, y[x + 5]));
            const uint32_t w3 = pack_bf16(fmaf(o[x + 6], a1, y[x + 6]), fmaf(o[x + 7], a1, y[x + 7]));
            st_async16(rdst + t * 512, w0, w1, w2, w3, rbar + 8 * (t >> 1));
            st_shared16(dst + t * 512, w0, w1, w2, w3);
            if (t & 1) {
                __syncwarp();
                if (lane == 0) mbar_arrive_n(bar(kBarOReady + (t >> 1)), 1);
            }
        }
    }
    if (tr) TRACE(g, 6);

    const int grp = bp * 4 + 2 * r + g, me = 2 * hkv + s;
    uint4* const pdst = g_box + ((size_t)(grp * 16 + 4 * w + (lane >> 3)) * 16 + me) * 64 + (lane & 7);
    {
        uint32_t a[64];
        const uint32_t src = sbase + kSlotO * kSlotBytes + (w * 16 * 32 + lane) * 16;
        mbar_wait(bar(kBarFull + 32 + g), 0);
        mbar_wait(bar(kBarFull + 34 + g), 0);
        const uint32_t wb0 = sbase + tile_slot(32 + g) * kSlotBytes, wb1 = sbase + tile_slot(34 + g) * kSlotBytes;
        auto load_group = [&](int gm) {
            mbar_wait(bar(kBarOReady + gm), 0);
#pragma unroll
            for (int u = 0; u < 4; u++) {
                const int j = u >> 1, t = 2 * gm + (u & 1), x = 16 * gm + 4 * u;
                ld_shared16(src + (j * 8 + t) * 512, a[x], a[x + 1], a[x + 2], a[x + 3]);
            }
#pragma unroll
            for (int x = 16 * gm; x < 16 * gm + 16; x += 4) asm volatile("" : "+r"(a[x]), "+r"(a[x + 1]), "+r"(a[x + 2]), "+r"(a[x + 3])::"memory");
        };
        if (g == 0) {
            float acc[64];
#pragma unroll
            for (int gm = 0; gm < 4; gm++) {
                load_group(gm);
                if (gm == 0 && tr) TRACE(g, 7);
                wg_fence();
#pragma unroll
                for (int u = 0; u < 4; u++) {
                    const int j = u >> 1, t = 2 * gm + (u & 1), x = 16 * gm + 4 * u;
                    wgmma_rs_n128<1>(acc, a[x], a[x + 1], a[x + 2], a[x + 3], make_desc((j ? wb1 : wb0) + t * 2048, kHalfBytes, 1024),
                                     (gm | u) != 0);
                }
                wg_commit();
            }
            bar_arrive(5, 256);
            wg_wait<0>();
            fence_regs(acc);
            if (tr) TRACE(g, 16);
            mbar_wait(bar(kBarMbox), 0);
#pragma unroll
            for (int t = 0; t < 8; t++)
                st_chunk(pdst + t * 8, pack_bf16(acc[8 * t], acc[8 * t + 1]), pack_bf16(acc[8 * t + 2], acc[8 * t + 3]),
                         pack_bf16(acc[8 * t + 4], acc[8 * t + 5]), pack_bf16(acc[8 * t + 6], acc[8 * t + 7]));
        } else {
            float acc0[32], acc1[32];
#pragma unroll
            for (int gm = 0; gm < 4; gm++) load_group(gm);
            mbar_wait(bar(kBarMbox), 0);
            bar_sync(5, 256);
            if (tr) TRACE(g, 7);
            wg_fence();
#pragma unroll
            for (int u = 0; u < 16; u++) {
                const int j = (u >> 1) & 1, t = 2 * (u >> 2) + (u & 1), x = 4 * u;
                wgmma_rs_n64(acc0, a[x], a[x + 1], a[x + 2], a[x + 3], make_desc((j ? wb1 : wb0) + t * 2048, kHalfBytes, 1024), u != 0);
            }
            wg_commit();
#pragma unroll
            for (int u = 0; u < 16; u++) {
                const int j = (u >> 1) & 1, t = 2 * (u >> 2) + (u & 1), x = 4 * u;
                wgmma_rs_n64(acc1, a[x], a[x + 1], a[x + 2], a[x + 3],
                             make_desc((j ? wb1 : wb0) + kHalfBytes + t * 2048, kHalfBytes, 1024), u != 0);
            }
            wg_commit();
            wg_wait<1>();
            fence_regs(acc0);
#pragma unroll
            for (int t = 0; t < 4; t++)
                st_chunk(pdst + t * 8, pack_bf16(acc0[8 * t], acc0[8 * t + 1]), pack_bf16(acc0[8 * t + 2], acc0[8 * t + 3]),
                         pack_bf16(acc0[8 * t + 4], acc0[8 * t + 5]), pack_bf16(acc0[8 * t + 6], acc0[8 * t + 7]));
            wg_wait<0>();
            fence_regs(acc1);
            if (tr) TRACE(g, 16);
#pragma unroll
            for (int t = 0; t < 4; t++)
                st_chunk(pdst + (4 + t) * 8, pack_bf16(acc1[8 * t], acc1[8 * t + 1]), pack_bf16(acc1[8 * t + 2], acc1[8 * t + 3]),
                         pack_bf16(acc1[8 * t + 4], acc1[8 * t + 5]), pack_bf16(acc1[8 * t + 6], acc1[8 * t + 7]));
        }
    }
    if (tr) TRACE(g, 17);

    {
        const int sh = lane >> 4, o16 = lane & 15;
        const uint4* src = g_box + ((size_t)(grp * 16 + me) * 16 + 8 * sh) * 64 + 16 * w + o16;
        uint32_t v[32];
#pragma unroll
        for (int k = 0; k < 8; k++) ld_chunk(src + k * 64, v[4 * k], v[4 * k + 1], v[4 * k + 2], v[4 * k + 3]);
        uint32_t it = 0;
        while (true) {
            bool pending = false;
#pragma unroll
            for (int k = 0; k < 8; k++) pending = pending || (v[4 * k] == 0u);
            if (!__any_sync(0xffffffffu, pending) || ++it > kSpinLimit) break;
#pragma unroll
            for (int k = 0; k < 8; k++)
                if (v[4 * k] == 0u) ld_chunk(src + k * 64, v[4 * k], v[4 * k + 1], v[4 * k + 2], v[4 * k + 3]);
        }
        float f[8];
#pragma unroll
        for (int e = 0; e < 4; e++) {
            float lo = 0.f, hi = 0.f;
#pragma unroll
            for (int k = 0; k < 8; k++) {
                lo += bf_lo(v[4 * k + e]);
                hi += bf_hi(v[4 * k + e]);
            }
            f[2 * e] = lo;
            f[2 * e + 1] = hi;
        }
        float y[4];
#pragma unroll
        for (int e = 0; e < 4; e++) {
            const int mine = (e >> 1) * 4 + (e & 1), other = mine + 2;
            const float keep = sh ? f[other] : f[mine], give = sh ? f[mine] : f[other];
            const float got = __shfl_xor_sync(0xffffffffu, give, 16);
            y[e] = sh ? got + keep : keep + got;
        }
        const int t = 2 * w + (o16 >> 3), l8 = o16 & 7, c = l8 & 3;
        const int mrow = 16 * (me >> 2) + 2 * (me & 3) + (l8 >> 2) + 8 * sh;
        uint32_t* o32 = reinterpret_cast<uint32_t*>(out) + (((2 * bp * kSq + mrow) * kD + 256 * r + 128 * g + 16 * t + 2 * c) >> 1);
        o32[0] = pack_bf16(y[0], y[1]);
        o32[4] = pack_bf16(y[2], y[3]);
    }
    if (tr) TRACE(g, 18);
}

typedef CUresult (*EncodeTiledFn)(CUtensorMap*, CUtensorMapDataType, cuuint32_t, void*, const cuuint64_t*, const cuuint64_t*,
                                  const cuuint32_t*, const cuuint32_t*, CUtensorMapInterleave, CUtensorMapSwizzle,
                                  CUtensorMapL2promotion, CUtensorMapFloatOOBfill);

bool make_map(EncodeTiledFn fn, CUtensorMap* m, const void* ptr, uint64_t cols, uint64_t rows, uint32_t box_cols, uint32_t box_rows) {
    cuuint64_t dims[2] = {cols, rows};
    cuuint64_t strides[1] = {cols * 2};
    cuuint32_t box[2] = {box_cols, box_rows};
    cuuint32_t es[2] = {1, 1};
    return fn(m, CU_TENSOR_MAP_DATA_TYPE_BFLOAT16, 2, const_cast<void*>(ptr), dims, strides, box, es, CU_TENSOR_MAP_INTERLEAVE_NONE,
              CU_TENSOR_MAP_SWIZZLE_128B, CU_TENSOR_MAP_L2_PROMOTION_L2_256B, CU_TENSOR_MAP_FLOAT_OOB_FILL_NONE) == CUDA_SUCCESS;
}

}

extern "C" void kernel_launch(void* const* d_in, const int* in_sizes, int n_in, void* d_out, int out_size) {
    (void)in_sizes;
    (void)n_in;
    (void)out_size;
    static EncodeTiledFn encode = nullptr;
    if (!encode) {
        void* fn = nullptr;
        cudaDriverEntryPointQueryResult qr;
        if (cudaGetDriverEntryPoint("cuTensorMapEncodeTiled", &fn, cudaEnableDefault, &qr) != cudaSuccess || !fn) return;
        encode = (EncodeTiledFn)fn;
        cudaFuncSetAttribute(fused_swa_kernel, cudaFuncAttributeMaxDynamicSharedMemorySize, (int)kSmemBytes);
    }
    Params prm;
    bool ok = make_map(encode, &prm.k, d_in[1], kDh, (uint64_t)kB * kHkv * kSk, 64, 128);
    ok = ok && make_map(encode, &prm.v, d_in[2], kDh, (uint64_t)kB * kHkv * kSk, 64, 128);
    ok = ok && make_map(encode, &prm.wo, d_in[4], kD, kHq * kDh, 64, 128);
    ok = ok && make_map(encode, &prm.wq, d_in[3], kHq * kDh, kD, 64, 128);
    ok = ok && make_map(encode, &prm.x, d_in[0], kD, kB * kSq, 64, 64);
    if (!ok) return;

    cudaLaunchConfig_t cfg = {};
    cfg.gridDim = dim3(kCtas);
    cfg.blockDim = dim3(kThreads);
    cfg.dynamicSmemBytes = kSmemBytes;
    cfg.stream = cudaStreamPerThread;
    cudaLaunchAttribute at[1];
    at[0].id = cudaLaunchAttributeClusterDimension;
    at[0].val.clusterDim.x = 2;
    at[0].val.clusterDim.y = 1;
    at[0].val.clusterDim.z = 1;
    cfg.attrs = at;
    cfg.numAttrs = 1;
    cudaLaunchKernelEx(&cfg, fused_swa_kernel, prm, (const __nv_bfloat16*)d_in[1], (const __nv_bfloat16*)d_in[2], (__nv_bfloat16*)d_out);
}
```

```cpp
#include <cuda_runtime.h>
#include <cuda_bf16.h>
#include <cuda.h>
#include <stdint.h>

namespace {

constexpr int kB = 8, kSq = 32, kD = 512, kHq = 32, kHkv = 8, kSk = 8192, kDh = 128, kW = 2048;
constexpr int kSlots = 7;
constexpr uint32_t kSlotBytes = 32768;
constexpr uint32_t kHalfBytes = 16384;
constexpr int kThreads = 384;
constexpr int kCtas = 128;
constexpr uint32_t kBarOff = kSlots * kSlotBytes;
constexpr uint32_t kMlOff = kBarOff + 512;
constexpr uint32_t kSmemBytes = kMlOff + 2048;
constexpr int kNumTiles = 36;
constexpr uint32_t kPeerOff = kBarOff + 496;
constexpr int kBarFull = 0;
constexpr int kBarEmpty = 36;
constexpr int kBarXw = 43;
constexpr int kBarQFree = 49;
constexpr int kBarQReady = 50;
constexpr int kBarOFree = 51;
constexpr int kBarOReady = 52;
constexpr int kBarMbox = 56;
constexpr int kBarV15b = 57;
constexpr int kBarWa = 58;
constexpr int kSlotWq0 = 6, kSlotWq1 = 1, kSlotXa = 2, kSlotWq2 = 3, kSlotWq3 = 4, kSlotXb = 5;
constexpr int kSlotQ = kSlotWq0;
constexpr int kSlotDump = 1;
constexpr int kSlotO = 0;
constexpr int kInFlight = 4;
constexpr int kLockStep0 = 4;
constexpr int kClearTile0 = 4, kClearPerTile = 2;
constexpr uint32_t kSpinLimit = 1u << 20;

__device__ uint4 g_box[16 * 16 * 16 * 64];
__device__ unsigned int g_cleared[4 * 32];


__device__ __forceinline__ uint32_t smem_u32(const void* p) { return (uint32_t)__cvta_generic_to_shared(p); }
__device__ __forceinline__ void mbar_init(uint32_t bar, uint32_t cnt) {
    asm volatile("mbarrier.init.shared::cta.b64 [%0], %1;" ::"r"(bar), "r"(cnt));
}
__device__ __forceinline__ void mbar_expect_tx(uint32_t bar, uint32_t bytes) {
    asm volatile("mbarrier.arrive.expect_tx.shared::cta.b64 _, [%0], %1;" ::"r"(bar), "r"(bytes) : "memory");
}
__device__ __forceinline__ void mbar_arrive_n(uint32_t bar, uint32_t n) {
    asm volatile("mbarrier.arrive.shared::cta.b64 _, [%0], %1;" ::"r"(bar), "r"(n) : "memory");
}
__device__ __forceinline__ bool mbar_try(uint32_t bar, uint32_t parity) {
    uint32_t ok;
    asm volatile(
        "{\n.reg .pred p;\nmbarrier.try_wait.parity.shared::cta.b64 p, [%1], %2;\nselp.b32 %0, 1, 0, p;\n}"
        : "=r"(ok)
        : "r"(bar), "r"(parity)
        : "memory");
    return ok;
}
__device__ __forceinline__ void mbar_wait(uint32_t bar, uint32_t parity) {
    uint32_t it = 0;
    while (!mbar_try(bar, parity)) {
        if (++it > kSpinLimit) break;
    }
}
__device__ __forceinline__ void tma_2d(uint32_t dst, const CUtensorMap* map, int c0, int c1, uint32_t bar) {
    asm volatile(
        "cp.async.bulk.tensor.2d.shared::cluster.global.mbarrier::complete_tx::bytes [%0], [%1, {%3, %4}], [%2];" ::"r"(dst),
        "l"(map), "r"(bar), "r"(c0), "r"(c1)
        : "memory");
}
__device__ __forceinline__ void tma_2d_hint(uint32_t dst, const CUtensorMap* map, int c0, int c1, uint32_t bar, uint64_t pol) {
    asm volatile(
        "cp.async.bulk.tensor.2d.shared::cluster.global.mbarrier::complete_tx::bytes.L2::cache_hint [%0], [%1, {%3, %4}], [%2], %5;" ::"r"(dst),
        "l"(map), "r"(bar), "r"(c0), "r"(c1), "l"(pol)
        : "memory");
}
__device__ __forceinline__ uint64_t policy_evict_first() {
    uint64_t pol;
    asm volatile("createpolicy.fractional.L2::evict_first.b64 %0, 1.0;" : "=l"(pol));
    return pol;
}
__device__ __forceinline__ uint32_t mapa(uint32_t addr, uint32_t rank) {
    uint32_t r;
    asm volatile("mapa.shared::cluster.u32 %0, %1, %2;" : "=r"(r) : "r"(addr), "r"(rank));
    return r;
}
__device__ __forceinline__ void mbar_arrive_remote(uint32_t cluster_addr) {
    asm volatile("mbarrier.arrive.shared::cluster.b64 _, [%0];" ::"r"(cluster_addr) : "memory");
}
__device__ __forceinline__ void st_async16(uint32_t cluster_addr, uint32_t w0, uint32_t w1, uint32_t w2, uint32_t w3, uint32_t cluster_bar) {
    asm volatile("st.async.weak.shared::cluster.mbarrier::complete_tx::bytes.v4.b32 [%0], {%1, %2, %3, %4}, [%5];" ::"r"(cluster_addr),
                 "r"(w0), "r"(w1), "r"(w2), "r"(w3), "r"(cluster_bar)
                 : "memory");
}
__device__ __forceinline__ void st_shared16(uint32_t addr, uint32_t w0, uint32_t w1, uint32_t w2, uint32_t w3) {
    asm volatile("st.shared.v4.b32 [%0], {%1, %2, %3, %4};" ::"r"(addr), "r"(w0), "r"(w1), "r"(w2), "r"(w3) : "memory");
}
__device__ __forceinline__ void ld_shared16(uint32_t addr, uint32_t& w0, uint32_t& w1, uint32_t& w2, uint32_t& w3) {
    asm volatile("ld.shared.v4.b32 {%0, %1, %2, %3}, [%4];" : "=r"(w0), "=r"(w1), "=r"(w2), "=r"(w3) : "r"(addr) : "memory");
}
__device__ __forceinline__ void cluster_arrive() { asm volatile("barrier.cluster.arrive.relaxed.aligned;" ::: "memory"); }
__device__ __forceinline__ void cluster_wait() { asm volatile("barrier.cluster.wait.acquire.aligned;" ::: "memory"); }
__device__ __forceinline__ void bar_sync(int id, int n) { asm volatile("bar.sync %0, %1;" ::"r"(id), "r"(n) : "memory"); }
__device__ __forceinline__ void bar_arrive(int id, int n) { asm volatile("bar.arrive %0, %1;" ::"r"(id), "r"(n) : "memory"); }

__device__ __forceinline__ uint32_t pack_bf16(float lo, float hi) {
    uint32_t r;
    asm("cvt.rn.bf16x2.f32 %0, %1, %2;" : "=r"(r) : "f"(hi), "f"(lo));
    return r;
}
__device__ __forceinline__ float ex2(float x) {
    float y;
    asm("ex2.approx.ftz.f32 %0, %1;" : "=f"(y) : "f"(x));
    return y;
}
__device__ __forceinline__ float bf_lo(uint32_t w) { return __uint_as_float(w << 16); }
__device__ __forceinline__ float bf_hi(uint32_t w) { return __uint_as_float(w & 0xffff0000u); }

__device__ __forceinline__ void st_chunk(uint4* p, uint32_t w0, uint32_t w1, uint32_t w2, uint32_t w3) {
    w0 = (w0 == 0u) ? 0x80000000u : w0;
    asm volatile(
        "{\n.reg .b128 v;\n.reg .b64 lo, hi;\nmov.b64 lo, {%1, %2};\nmov.b64 hi, {%3, %4};\nmov.b128 v, {lo, hi};\n"
        "st.relaxed.gpu.global.b128 [%0], v;\n}" ::"l"(p),
        "r"(w0), "r"(w1), "r"(w2), "r"(w3)
        : "memory");
}
__device__ __forceinline__ void ld_chunk(const uint4* p, uint32_t& w0, uint32_t& w1, uint32_t& w2, uint32_t& w3) {
    asm volatile(
        "{\n.reg .b128 v;\n.reg .b64 lo, hi;\nld.relaxed.gpu.global.b128 v, [%4];\nmov.b128 {lo, hi}, v;\n"
        "mov.b64 {%0, %1}, lo;\nmov.b64 {%2, %3}, hi;\n}"
        : "=r"(w0), "=r"(w1), "=r"(w2), "=r"(w3)
        : "l"(p)
        : "memory");
}

__device__ __forceinline__ uint64_t make_desc(uint32_t addr, uint32_t lbo_bytes, uint32_t sbo_bytes) {
    return (uint64_t)((addr & 0x3FFFFu) >> 4) | ((uint64_t)(lbo_bytes >> 4) << 16) | ((uint64_t)(sbo_bytes >> 4) << 32) |
           (1ull << 62);
}
__device__ __forceinline__ void wg_fence() { asm volatile("wgmma.fence.sync.aligned;" ::: "memory"); }
__device__ __forceinline__ void wg_commit() { asm volatile("wgmma.commit_group.sync.aligned;" ::: "memory"); }
template <int N>
__device__ __forceinline__ void wg_wait() {
    asm volatile("wgmma.wait_group.sync.aligned %0;" ::"n"(N) : "memory");
}
template <int N>
__device__ __forceinline__ void fence_regs(float (&r)[N]) {
#pragma unroll
    for (int i = 0; i < N; i++) asm volatile("" : "+f"(r[i])::"memory");
}
template <int OFF, int CNT, int N>
__device__ __forceinline__ void fence_regs_part(float (&r)[N]) {
#pragma unroll
    for (int i = OFF; i < OFF + CNT; i++) asm volatile("" : "+f"(r[i])::"memory");
}
template <int N>
__device__ __forceinline__ void fence_regs(uint32_t (&r)[N]) {
#pragma unroll
    for (int i = 0; i < N; i++) asm volatile("" : "+r"(r[i])::"memory");
}

#define ACC8(d, o) "+f"(d[o + 0]), "+f"(d[o + 1]), "+f"(d[o + 2]), "+f"(d[o + 3]), "+f"(d[o + 4]), "+f"(d[o + 5]), "+f"(d[o + 6]), "+f"(d[o + 7])

template <int TRANS_B>
__device__ __forceinline__ void wgmma_rs_n128(float (&d)[64], uint32_t a0, uint32_t a1, uint32_t a2, uint32_t a3, uint64_t descB,
                                              int scale_d) {
    asm volatile(
        "{\n.reg .pred p;\nsetp.ne.b32 p, %69, 0;\n"
        "wgmma.mma_async.sync.aligned.m64n128k16.f32.bf16.bf16 "
        "{%0, %1, %2, %3, %4, %5, %6, %7, %8, %9, %10, %11, %12, %13, %14, %15, "
        "%16, %17, %18, %19, %20, %21, %22, %23, %24, %25, %26, %27, %28, %29, %30, %31, "
        "%32, %33, %34, %35, %36, %37, %38, %39, %40, %41, %42, %43, %44, %45, %46, %47, "
        "%48, %49, %50, %51, %52, %53, %54, %55, %56, %57, %58, %59, %60, %61, %62, %63}, "
        "{%64, %65, %66, %67}, %68, p, 1, 1, %70;\n}"
        : ACC8(d, 0), ACC8(d, 8), ACC8(d, 16), ACC8(d, 24), ACC8(d, 32), ACC8(d, 40), ACC8(d, 48), ACC8(d, 56)
        : "r"(a0), "r"(a1), "r"(a2), "r"(a3), "l"(descB), "r"(scale_d), "n"(TRANS_B));
}
__device__ __forceinline__ void wgmma_rs_n64(float (&d)[32], uint32_t a0, uint32_t a1, uint32_t a2, uint32_t a3, uint64_t descB,
                                             int scale_d) {
    asm volatile(
        "{\n.reg .pred p;\nsetp.ne.b32 p, %37, 0;\n"
        "wgmma.mma_async.sync.aligned.m64n64k16.f32.bf16.bf16 "
        "{%0, %1, %2, %3, %4, %5, %6, %7, %8, %9, %10, %11, %12, %13, %14, %15, "
        "%16, %17, %18, %19, %20, %21, %22, %23, %24, %25, %26, %27, %28, %29, %30, %31}, "
        "{%32, %33, %34, %35}, %36, p, 1, 1, 1;\n}"
        : ACC8(d, 0), ACC8(d, 8), ACC8(d, 16), ACC8(d, 24)
        : "r"(a0), "r"(a1), "r"(a2), "r"(a3), "l"(descB), "r"(scale_d));
}
template <int OFF>
__device__ __forceinline__ void wgmma_rs_n64_half(float (&d)[64], uint32_t a0, uint32_t a1, uint32_t a2, uint32_t a3, uint64_t descB) {
    asm volatile(
        "wgmma.mma_async.sync.aligned.m64n64k16.f32.bf16.bf16 "
        "{%0, %1, %2, %3, %4, %5, %6, %7, %8, %9, %10, %11, %12, %13, %14, %15, "
        "%16, %17, %18, %19, %20, %21, %22, %23, %24, %25, %26, %27, %28, %29, %30, %31}, "
        "{%32, %33, %34, %35}, %36, 1, 1, 1, 1;\n"
        : ACC8(d, OFF), ACC8(d, OFF + 8), ACC8(d, OFF + 16), ACC8(d, OFF + 24)
        : "r"(a0), "r"(a1), "r"(a2), "r"(a3), "l"(descB));
}
__device__ __forceinline__ void wgmma_ss_n64(float (&d)[32], uint64_t descA, uint64_t descB, int scale_d) {
    asm volatile(
        "{\n.reg .pred p;\nsetp.ne.b32 p, %34, 0;\n"
        "wgmma.mma_async.sync.aligned.m64n64k16.f32.bf16.bf16 "
        "{%0, %1, %2, %3, %4, %5, %6, %7, %8, %9, %10, %11, %12, %13, %14, %15, "
        "%16, %17, %18, %19, %20, %21, %22, %23, %24, %25, %26, %27, %28, %29, %30, %31}, "
        "%32, %33, p, 1, 1, 0, 1;\n}"
        : ACC8(d, 0), ACC8(d, 8), ACC8(d, 16), ACC8(d, 24)
        : "l"(descA), "l"(descB), "r"(scale_d));
}

__device__ __forceinline__ int tile_slot(int t) { return t < 25 ? t % kSlots : (t < 32 ? (t - 25) & 3 : (t == 35 ? 3 : t - 28)); }

__device__ __forceinline__ int issue_order(int n) { return n == 33 ? 34 : (n == 34 ? 33 : n); }

struct alignas(64) Params {
    CUtensorMap k, v, wo, wq, x;
};

__global__ void __launch_bounds__(kThreads, 1)
fused_swa_kernel(const __nv_bfloat16* __restrict__ wq, const __nv_bfloat16* __restrict__ xp, __nv_bfloat16* __restrict__ out,
                 const __grid_constant__ Params prm) {
    extern __shared__ __align__(1024) uint8_t smem[];
    const uint32_t sbase = smem_u32(smem);
    const uint32_t bars = sbase + kBarOff;
    auto bar = [&](int i) { return bars + 8 * i; };

    const int tid = threadIdx.x;
    const int warp = __shfl_sync(0xffffffffu, tid >> 5, 0), lane = tid & 31;
    const int cta = blockIdx.x;
    const int r = cta & 1;
    int pc, s;
    {
        const int c = cta >> 1;
        int k, h;
        const int u = c - 36, qd = (u * 37) >> 8, hi = c >= 36, lo = c < 4;
        const int k1 = (c - 4) >> 3, h1 = (c - 4) & 7, k2 = 4 + qd, h2 = u - 7 * qd + 1;
        asm("{\n.reg .pred p, q;\nsetp.ne.s32 p, %2, 0;\nsetp.ne.s32 q, %3, 0;\n"
            "selp.s32 %0, %4, %5, p;\nselp.s32 %0, %8, %0, q;\nselp.s32 %1, %6, %7, p;\nselp.s32 %1, 0, %1, q;\n}"
            : "=&r"(k), "=&r"(h)
            : "r"(hi), "r"(lo), "r"(k2), "r"(k1), "r"(h2), "r"(h1), "r"(4 + c));
        pc = (k >> 1) * 8 + h, s = k & 1;
    }
    const int bp = pc >> 3, hkv = pc & 7;
    const int b = 2 * bp + r;
    const int head0 = 4 * hkv + 2 * s;

    if (tid < 256) {
        const int j = tid & 7, row = (tid >> 3) & 15, g = tid >> 7;
        const uint32_t sw = (uint32_t)(j ^ (row & 7)) << 4;
        const uint32_t dw = sbase + kSlotWq0 * kSlotBytes + g * kHalfBytes + row * 128 + sw;
        const __nv_bfloat16* gw = wq + ((uint32_t)row * (kHq * kDh) + (head0 + r) * 128 + g * 64 + j * 8);
        const int xr = (tid >> 3) & 31;
        const uint32_t dx = sbase + kSlotXa * kSlotBytes + xr * 128 + sw;
        const __nv_bfloat16* gx = xp + ((uint32_t)(64 * bp + xr) * kD + j * 8);
#pragma unroll
        for (int i = 0; i < 8; i++)
            asm volatile("cp.async.cg.shared.global [%0], [%1], 16;" ::"r"(dw + i * 2048), "l"(gw + (size_t)(16 * i) * (kHq * kDh)) : "memory");
#pragma unroll
        for (int i = 0; i < 4; i++)
            asm volatile("cp.async.cg.shared.global [%0], [%1], 16;" ::"r"(dx + (i >> 1) * 8192 + (i & 1) * 4096),
                         "l"(gx + (i >> 1) * 64 + (i & 1) * 32 * kD)
                         : "memory");
        asm volatile("cp.async.commit_group;" ::: "memory");
    }
    if (warp < 8) {
    asm volatile("setmaxnreg.inc.sync.aligned.u32 232;");
    const int g = warp >> 2;
    const int w = warp & 3;
    const int wtid = tid & 127;
    cluster_arrive();
    cluster_wait();

    {
        float acc[32];
#pragma unroll
        for (int c = 0; c < 4; c++) {
            const int slotW = c == 0 ? kSlotWq0 : (c == 1 ? kSlotWq1 : (c == 2 ? kSlotWq2 : kSlotWq3));
            const int slotX = c < 2 ? kSlotXa : kSlotXb;
            if (c == 0) {
                asm volatile("cp.async.wait_group 0;" ::: "memory");
                asm volatile("fence.proxy.async.shared::cta;" ::: "memory");
                bar_sync(2, 256);
            } else {
                if (c < 3) mbar_wait(bar(kBarXw + 3 + c), 0);
                mbar_wait(bar(kBarXw + c), 0);
            }
            wg_fence();
            const uint32_t wb = sbase + slotW * kSlotBytes + g * kHalfBytes;
            const uint32_t xb = sbase + slotX * kSlotBytes + (c & 1) * kHalfBytes;
#pragma unroll
            for (int kk = 0; kk < 8; kk++)
                wgmma_ss_n64(acc, make_desc(xb + (kk >> 2) * 8192 + (kk & 3) * 32, 16, 1024), make_desc(wb + kk * 2048, kHalfBytes, 1024),
                             (c | kk) != 0);
            wg_commit();
            wg_wait<0>();
            fence_regs(acc);
            if (lane == 0) {
                if (c == 0) {
                    mbar_arrive_remote(mapa(bar(kBarQFree), 0));
                    mbar_arrive_remote(mapa(bar(kBarQFree), 1));
                } else {
                    mbar_arrive_n(bar(kBarEmpty + slotW), 1);
                    if (c & 1) mbar_arrive_n(bar(kBarEmpty + slotX), 1);
                }
            }
        }
        mbar_wait(bar(kBarQFree), 0);
        const uint32_t dst = sbase + kSlotQ * kSlotBytes + (((r * 2 + (w & 1)) * 8 + 4 * g) * 32 + lane) * 16;
        if ((w >> 1) == r) {
#pragma unroll
            for (int t = 0; t < 4; t++)
                st_shared16(dst + t * 512, pack_bf16(acc[8 * t], acc[8 * t + 1]), pack_bf16(acc[8 * t + 2], acc[8 * t + 3]),
                            pack_bf16(acc[8 * t + 4], acc[8 * t + 5]), pack_bf16(acc[8 * t + 6], acc[8 * t + 7]));
            __syncwarp();
            if (lane == 0) mbar_arrive_n(bar(kBarQReady), 1);
        } else {
            const uint32_t rdst = mapa(dst, r ^ 1), rbar = mapa(bar(kBarQReady), r ^ 1);
#pragma unroll
            for (int t = 0; t < 4; t++)
                st_async16(rdst + t * 512, pack_bf16(acc[8 * t], acc[8 * t + 1]), pack_bf16(acc[8 * t + 2], acc[8 * t + 3]),
                           pack_bf16(acc[8 * t + 4], acc[8 * t + 5]), pack_bf16(acc[8 * t + 6], acc[8 * t + 7]), rbar);
        }
    }

    uint32_t q[32];
    {
        mbar_wait(bar(kBarQReady), 0);
        const uint32_t src = sbase + kSlotQ * kSlotBytes + (w * 8 * 32 + lane) * 16;
#pragma unroll
        for (int t = 0; t < 8; t++) ld_shared16(src + t * 512, q[4 * t], q[4 * t + 1], q[4 * t + 2], q[4 * t + 3]);
        fence_regs(q);
        __syncwarp();
        if (lane == 0) mbar_arrive_n(bar(kBarEmpty + kSlotQ), 1);
    }

    const float sc = 0.08838834764831845f * 1.4426950408889634f;
    float o[64];
#pragma unroll
    for (int i = 0; i < 64; i++) o[i] = 0.f;
    float m0 = -INFINITY, m1 = -INFINITY, l0 = 0.f, l1 = 0.f;

    auto qk_softmax = [&](int tK, uint32_t (&pf)[32]) {
        const int sK = tile_slot(tK);
        float sacc[64];
        mbar_wait(bar(kBarFull + tK), 0);
        fence_regs(q);
        wg_fence();
        {
            const uint32_t kb = sbase + sK * kSlotBytes;
#pragma unroll
            for (int kk = 0; kk < 8; kk++) {
                const uint64_t db = make_desc(kb + (kk >> 2) * kHalfBytes + (kk & 3) * 32, 16, 1024);
                wgmma_rs_n128<0>(sacc, q[4 * kk], q[4 * kk + 1], q[4 * kk + 2], q[4 * kk + 3], db, kk != 0);
            }
        }
        wg_commit();
        wg_wait<0>();
        fence_regs(sacc);
        if (lane == 0) {
            if (tK != 29) mbar_arrive_n(bar(kBarEmpty + sK), 2);
            else mbar_arrive_remote(mapa(bar(kBarOFree), r ^ 1));
        }

        float x0 = sacc[0], x1 = sacc[2];
#pragma unroll
        for (int j = 0; j < 16; j++) {
            x0 = fmaxf(x0, fmaxf(sacc[4 * j], sacc[4 * j + 1]));
            x1 = fmaxf(x1, fmaxf(sacc[4 * j + 2], sacc[4 * j + 3]));
        }
        x0 = fmaxf(x0, __shfl_xor_sync(0xffffffffu, x0, 1));
        x1 = fmaxf(x1, __shfl_xor_sync(0xffffffffu, x1, 1));
        x0 = fmaxf(x0, __shfl_xor_sync(0xffffffffu, x0, 2));
        x1 = fmaxf(x1, __shfl_xor_sync(0xffffffffu, x1, 2));
        const float n0 = fmaxf(m0, x0), n1 = fmaxf(m1, x1);
        const float c0 = ex2((m0 - n0) * sc), c1 = ex2((m1 - n1) * sc);
        m0 = n0;
        m1 = n1;
        const float ms0 = n0 * sc, ms1 = n1 * sc;
        float r0 = 0.f, r1 = 0.f;
#pragma unroll
        for (int j = 0; j < 16; j++) {
            const float p0 = ex2(fmaf(sacc[4 * j], sc, -ms0));
            const float p1 = ex2(fmaf(sacc[4 * j + 1], sc, -ms0));
            const float p2 = ex2(fmaf(sacc[4 * j + 2], sc, -ms1));
            const float p3 = ex2(fmaf(sacc[4 * j + 3], sc, -ms1));
            r0 += p0 + p1;
            r1 += p2 + p3;
            pf[2 * j] = pack_bf16(p0, p1);
            pf[2 * j + 1] = pack_bf16(p2, p3);
        }
        l0 = l0 * c0 + r0;
        l1 = l1 * c1 + r1;
#pragma unroll
        for (int j = 0; j < 16; j++) {
            o[4 * j] *= c0;
            o[4 * j + 1] *= c0;
            o[4 * j + 2] *= c1;
            o[4 * j + 3] *= c1;
        }
    };

#pragma unroll 1
    for (int i = 0; i < 8 - g; i++) {
        const int tK = i < 7 ? 4 * i + 2 * g : 28, tV = i < 7 ? tK + 1 : 30;
        uint32_t pf[32];
        qk_softmax(tK, pf);
        if (i == 7) {
            *reinterpret_cast<float4*>(smem + kMlOff + wtid * 16) = make_float4(m0, m1, l0, l1);
            bar_arrive(6, 256);
        }
        mbar_wait(bar(kBarFull + tV), 0);
        fence_regs(o);
        fence_regs(pf);
        wg_fence();
        const uint32_t vb = sbase + tile_slot(tV) * kSlotBytes;
#pragma unroll
        for (int kk = 0; kk < 8; kk++)
            wgmma_rs_n128<1>(o, pf[4 * kk], pf[4 * kk + 1], pf[4 * kk + 2], pf[4 * kk + 3], make_desc(vb + kk * 2048, kHalfBytes, 1024), 1);
        wg_commit();
        wg_wait<0>();
        fence_regs(o);
        if (lane == 0 && tV < 28) mbar_arrive_n(bar(kBarEmpty + tile_slot(tV)), 2);
    }

    if (g == 0) {
        bar_sync(1, 128);
        float4* dump = reinterpret_cast<float4*>(smem + kSlotDump * kSlotBytes);
#pragma unroll
        for (int j = 0; j < 8; j++) dump[j * 128 + wtid] = make_float4(o[4 * j], o[4 * j + 1], o[4 * j + 2], o[4 * j + 3]);
        bar_arrive(3, 256);
#pragma unroll
        for (int j = 8; j < 16; j++) dump[j * 128 + wtid] = make_float4(o[4 * j], o[4 * j + 1], o[4 * j + 2], o[4 * j + 3]);
        bar_arrive(7, 256);
    } else {
        uint32_t pf[32];
        qk_softmax(29, pf);
        float a0, a1, b0, b1;
        auto merge_scales = [&]() {
            bar_sync(6, 256);
            const float4 ml = *reinterpret_cast<const float4*>(smem + kMlOff + wtid * 16);
            const float n0 = fmaxf(m0, ml.x), n1 = fmaxf(m1, ml.y);
            const float e0 = ex2((ml.x - n0) * sc), e1 = ex2((ml.y - n1) * sc);
            const float c0 = ex2((m0 - n0) * sc), c1 = ex2((m1 - n1) * sc);
            float t0 = fmaf(ml.z, e0, l0 * c0), t1 = fmaf(ml.w, e1, l1 * c1);
            t0 += __shfl_xor_sync(0xffffffffu, t0, 1);
            t1 += __shfl_xor_sync(0xffffffffu, t1, 1);
            t0 += __shfl_xor_sync(0xffffffffu, t0, 2);
            t1 += __shfl_xor_sync(0xffffffffu, t1, 2);
            const float inv0 = 1.f / t0, inv1 = 1.f / t1;
            a0 = c0 * inv0, a1 = c1 * inv1, b0 = e0 * inv0, b1 = e1 * inv1;
            asm volatile("" : "+f"(a0), "+f"(a1), "+f"(b0), "+f"(b1)::"memory");
        };
        merge_scales();
        const float4* dump = reinterpret_cast<const float4*>(smem + kSlotDump * kSlotBytes);
        const uint32_t dst = sbase + kSlotO * kSlotBytes + ((((2 * r + (w & 1)) * 2 + (w >> 1)) * 8) * 32 + lane) * 16;
        const uint32_t rdst = mapa(dst, r ^ 1), rbar = mapa(bar(kBarOReady), r ^ 1);
        auto publish = [&](int t, const float (&y)[32]) {
            const int x = 8 * t, z = 8 * (t & 3);
            const uint32_t w0 = pack_bf16(fmaf(o[x], a0, y[z]), fmaf(o[x + 1], a0, y[z + 1]));
            const uint32_t w1 = pack_bf16(fmaf(o[x + 2], a1, y[z + 2]), fmaf(o[x + 3], a1, y[z + 3]));
            const uint32_t w2 = pack_bf16(fmaf(o[x + 4], a0, y[z + 4]), fmaf(o[x + 5], a0, y[z + 5]));
            const uint32_t w3 = pack_bf16(fmaf(o[x + 6], a1, y[z + 6]), fmaf(o[x + 7], a1, y[z + 7]));
            st_async16(rdst + t * 512, w0, w1, w2, w3, rbar + 8 * (t >> 1));
            st_shared16(dst + t * 512, w0, w1, w2, w3);
            if (t & 1) {
                __syncwarp();
                if (lane == 0) mbar_arrive_n(bar(kBarOReady + (t >> 1)), 1);
            }
        };
        auto load_half = [&](int h, float (&y)[32]) {
#pragma unroll
            for (int j = 0; j < 8; j++) {
                const float4 v = dump[(8 * h + j) * 128 + wtid];
                y[4 * j] = v.x * b0, y[4 * j + 1] = v.y * b0, y[4 * j + 2] = v.z * b1, y[4 * j + 3] = v.w * b1;
            }
            fence_regs(y);
        };
        const uint32_t vb = sbase + tile_slot(31) * kSlotBytes;
        float y0[32], y1[32];
        mbar_wait(bar(kBarFull + 31), 0);
        fence_regs(o);
        fence_regs(pf);
        wg_fence();
#pragma unroll
        for (int kk = 0; kk < 8; kk++)
            wgmma_rs_n64_half<0>(o, pf[4 * kk], pf[4 * kk + 1], pf[4 * kk + 2], pf[4 * kk + 3], make_desc(vb + kk * 2048, kHalfBytes, 1024));
        wg_commit();
        bar_sync(3, 256);
        load_half(0, y0);
        mbar_wait(bar(kBarOFree), 0);
        wg_wait<0>();
        fence_regs_part<0, 32>(o);
        mbar_wait(bar(kBarV15b), 0);
        wg_fence();
#pragma unroll
        for (int t = 0; t < 4; t++) {
#pragma unroll
            for (int kk = 2 * t; kk < 2 * t + 2; kk++)
                wgmma_rs_n64_half<32>(o, pf[4 * kk], pf[4 * kk + 1], pf[4 * kk + 2], pf[4 * kk + 3],
                                      make_desc(vb + kHalfBytes + kk * 2048, kHalfBytes, 1024));
            if (t == 3) wg_commit();
            publish(t, y0);
        }
        bar_sync(7, 256);
        load_half(1, y1);
        wg_wait<0>();
        fence_regs_part<32, 32>(o);
#pragma unroll
        for (int t = 4; t < 8; t++) publish(t, y1);
    }

    const int grp = bp * 4 + 2 * r + g, me = 2 * hkv + s;
    uint4* const pdst = g_box + ((size_t)(grp * 16 + 4 * w + (lane >> 3)) * 16 + me) * 64 + (lane & 7);
    {
        uint32_t a[64];
        const uint32_t src = sbase + kSlotO * kSlotBytes + (w * 16 * 32 + lane) * 16;
        const uint32_t wb0 = sbase + tile_slot(32 + g) * kSlotBytes, wb1 = sbase + tile_slot(34 + g) * kSlotBytes;
        auto load_group = [&](int gm) {
            mbar_wait(bar(kBarOReady + gm), 0);
#pragma unroll
            for (int u = 0; u < 4; u++) {
                const int j = u >> 1, t = 2 * gm + (u & 1), x = 16 * gm + 4 * u;
                ld_shared16(src + (j * 8 + t) * 512, a[x], a[x + 1], a[x + 2], a[x + 3]);
            }
#pragma unroll
            for (int x = 16 * gm; x < 16 * gm + 16; x += 4) asm volatile("" : "+r"(a[x]), "+r"(a[x + 1]), "+r"(a[x + 2]), "+r"(a[x + 3])::"memory");
        };
        if (g == 0) {
            float acc[64];
#pragma unroll
            for (int gm = 0; gm < 4; gm++) {
                load_group(gm);
                if (gm == 0) mbar_wait(bar(kBarFull + 32), 0);
                if (gm == 2) mbar_wait(bar(kBarFull + 34), 0);
                wg_fence();
#pragma unroll
                for (int u = 0; u < 4; u++) {
                    const int j = u >> 1, t = 2 * gm + (u & 1), x = 16 * gm + 4 * u;
                    wgmma_rs_n128<1>(acc, a[x], a[x + 1], a[x + 2], a[x + 3], make_desc((j ? wb1 : wb0) + t * 2048, kHalfBytes, 1024),
                                     (gm | u) != 0);
                }
                wg_commit();
                if (gm == 2) bar_arrive(5, 256);
            }
            wg_wait<0>();
            fence_regs(acc);
            mbar_wait(bar(kBarMbox), 0);
#pragma unroll
            for (int t = 0; t < 8; t++)
                st_chunk(pdst + t * 8, pack_bf16(acc[8 * t], acc[8 * t + 1]), pack_bf16(acc[8 * t + 2], acc[8 * t + 3]),
                         pack_bf16(acc[8 * t + 4], acc[8 * t + 5]), pack_bf16(acc[8 * t + 6], acc[8 * t + 7]));
        } else {
            float acc0[32], acc1[32];
#pragma unroll
            for (int gm = 0; gm < 4; gm++) load_group(gm);
            mbar_wait(bar(kBarMbox), 0);
            mbar_wait(bar(kBarWa), 0);
            bar_sync(5, 256);
            auto mma8 = [&](float (&acc)[32], int half, int u0) {
                wg_fence();
#pragma unroll
                for (int u = u0; u < u0 + 8; u++) {
                    const int j = (u >> 1) & 1, t = 2 * (u >> 2) + (u & 1), x = 4 * u;
                    wgmma_rs_n64(acc, a[x], a[x + 1], a[x + 2], a[x + 3],
                                 make_desc((j ? wb1 : wb0) + half * kHalfBytes + t * 2048, kHalfBytes, 1024), u != 0);
                }
                wg_commit();
            };
            mma8(acc0, 0, 0);
            mbar_wait(bar(kBarFull + 33), 0);
            mma8(acc0, 0, 8);
            mbar_wait(bar(kBarWa + 1), 0);
            mma8(acc1, 1, 0);
            mbar_wait(bar(kBarFull + 35), 0);
            mma8(acc1, 1, 8);
            wg_wait<2>();
            fence_regs(acc0);
#pragma unroll
            for (int t = 0; t < 4; t++)
                st_chunk(pdst + t * 8, pack_bf16(acc0[8 * t], acc0[8 * t + 1]), pack_bf16(acc0[8 * t + 2], acc0[8 * t + 3]),
                         pack_bf16(acc0[8 * t + 4], acc0[8 * t + 5]), pack_bf16(acc0[8 * t + 6], acc0[8 * t + 7]));
            wg_wait<0>();
            fence_regs(acc1);
#pragma unroll
            for (int t = 0; t < 4; t++)
                st_chunk(pdst + (4 + t) * 8, pack_bf16(acc1[8 * t], acc1[8 * t + 1]), pack_bf16(acc1[8 * t + 2], acc1[8 * t + 3]),
                         pack_bf16(acc1[8 * t + 4], acc1[8 * t + 5]), pack_bf16(acc1[8 * t + 6], acc1[8 * t + 7]));
        }
    }

    {
        const int sh = lane >> 4, o16 = lane & 15;
        const uint4* src = g_box + ((size_t)(grp * 16 + me) * 16 + 8 * sh) * 64 + 16 * w + o16;
        uint32_t v[32];
        uint32_t it = 0;
#pragma unroll
        for (int k = 0; k < 8; k++) ld_chunk(src + k * 64, v[4 * k], v[4 * k + 1], v[4 * k + 2], v[4 * k + 3]);
        while (true) {
            bool pending = false;
#pragma unroll
            for (int k = 0; k < 8; k++) pending = pending || (v[4 * k] == 0u);
            const bool anyp = __any_sync(0xffffffffu, pending);
            if (!anyp || ++it > kSpinLimit) break;
#pragma unroll
            for (int k = 0; k < 8; k++)
                if (v[4 * k] == 0u) ld_chunk(src + k * 64, v[4 * k], v[4 * k + 1], v[4 * k + 2], v[4 * k + 3]);
        }
        float f[8];
#pragma unroll
        for (int e = 0; e < 4; e++) {
            float lo = 0.f, hi = 0.f;
#pragma unroll
            for (int k = 0; k < 8; k++) {
                lo += bf_lo(v[4 * k + e]);
                hi += bf_hi(v[4 * k + e]);
            }
            f[2 * e] = lo;
            f[2 * e + 1] = hi;
        }
        float y[4];
#pragma unroll
        for (int e = 0; e < 4; e++) {
            const int mine = (e >> 1) * 4 + (e & 1), other = mine + 2;
            const float keep = sh ? f[other] : f[mine], give = sh ? f[mine] : f[other];
            const float got = __shfl_xor_sync(0xffffffffu, give, 16);
            y[e] = sh ? got + keep : keep + got;
        }
        const int t = 2 * w + (o16 >> 3), l8 = o16 & 7, c = l8 & 3;
        const int mrow = 16 * (me >> 2) + 2 * (me & 3) + (l8 >> 2) + 8 * sh;
        uint32_t* o32 = reinterpret_cast<uint32_t*>(out) + (((2 * bp * kSq + mrow) * kD + 256 * r + 128 * g + 16 * t + 2 * c) >> 1);
        o32[0] = pack_bf16(y[0], y[1]);
        o32[4] = pack_bf16(y[2], y[3]);
    }
    return;
    }
    asm volatile("setmaxnreg.dec.sync.aligned.u32 40;");
    const int kv_row0 = (b * kHkv + hkv) * kSk + (kSk - kW);
    if (warp == 8) {
        if (lane == 0) {
            asm volatile("prefetch.tensormap [%0];" ::"l"(&prm.wq) : "memory");
            asm volatile("prefetch.tensormap [%0];" ::"l"(&prm.x) : "memory");
            asm volatile("prefetch.tensormap [%0];" ::"l"(&prm.k) : "memory");
#pragma unroll
            for (int i = 1; i < 6; i++) mbar_init(bar(kBarXw + i), 1);
            mbar_init(bar(kBarFull), 1);
            asm volatile("fence.mbarrier_init.release.cluster;" ::: "memory");
        }
        __syncwarp();
        cluster_arrive();
        if (lane == 0) {
            auto load_x = [&](int half, int slot) {
                const uint32_t fb = bar(kBarXw + 4 + half), dst = sbase + slot * kSlotBytes;
                mbar_expect_tx(fb, half ? kSlotBytes : kHalfBytes);
#pragma unroll
                for (int i = half ? 0 : 2; i < 4; i++) tma_2d(dst + i * 8192, &prm.x, 256 * half + 64 * i, 64 * bp, fb);
            };
            auto load_wq = [&](int chunk, int slot) {
                const uint32_t fb = bar(kBarXw + chunk), dst = sbase + slot * kSlotBytes;
                mbar_expect_tx(fb, kSlotBytes);
                tma_2d(dst, &prm.wq, (head0 + r) * 128, 128 * chunk, fb);
                tma_2d(dst + kHalfBytes, &prm.wq, (head0 + r) * 128 + 64, 128 * chunk, fb);
            };
            load_x(0, kSlotXa);
            load_wq(1, kSlotWq1);
            load_x(1, kSlotXb);
            load_wq(2, kSlotWq2);
            load_wq(3, kSlotWq3);
            const uint64_t pol = policy_evict_first();
            mbar_expect_tx(bar(kBarFull), kSlotBytes);
            tma_2d_hint(sbase, &prm.k, 0, kv_row0, bar(kBarFull), pol);
            tma_2d_hint(sbase + kHalfBytes, &prm.k, 64, kv_row0, bar(kBarFull), pol);
        }
        __syncwarp();
    }
    if (warp > 8) {
        if (warp == 9 && lane == 0) {
            asm volatile("prefetch.tensormap [%0];" ::"l"(&prm.k) : "memory");
            asm volatile("prefetch.tensormap [%0];" ::"l"(&prm.v) : "memory");
#pragma unroll
            for (int i = 1; i < kNumTiles; i++) mbar_init(bar(kBarFull + i), 1);
            asm volatile("fence.mbarrier_init.release.cluster;" ::: "memory");
        }
        if (warp == 10 && lane == 0) {
#pragma unroll
            for (int i = 0; i < kSlots; i++) mbar_init(bar(kBarEmpty + i), 8);
            mbar_init(bar(kBarQFree), 16);
            mbar_init(bar(kBarQReady), 5);
            mbar_init(bar(kBarOFree), 4);
#pragma unroll
            for (int i = 0; i < 4; i++) mbar_init(bar(kBarOReady + i), 5);
            mbar_init(bar(kBarMbox), 1);
            mbar_init(bar(kBarV15b), 1);
            mbar_init(bar(kBarWa), 1);
            mbar_init(bar(kBarWa + 1), 1);
            asm volatile("st.shared.u32 [%0], %1;" ::"r"(sbase + kPeerOff), "r"(0) : "memory");
            mbar_expect_tx(bar(kBarQReady), 8192);
#pragma unroll
            for (int i = 0; i < 4; i++) mbar_expect_tx(bar(kBarOReady + i), 4096);
            asm volatile("fence.mbarrier_init.release.cluster;" ::: "memory");
        }
        __syncwarp();
        cluster_arrive();
        cluster_wait();
        if (warp == 9) return;
        uint4* z = g_box + ((size_t)(bp * 4 + 2 * r) * 16 * 16 + 2 * hkv + s) * 64 + (tid & 63);
#pragma unroll 1
        for (int i = 0; i < 32; i += kClearPerTile) {
            if (i > 0) mbar_wait(bar(kBarFull + kClearTile0 + i / kClearPerTile), 0);
#pragma unroll
            for (int u = 0; u < kClearPerTile; u++) z[(i + u) * 16 * 64] = make_uint4(0, 0, 0, 0);
        }
        __threadfence();
        bar_sync(4, 64);
        if (warp == 10 && lane == 0) {
            unsigned int* cnt = &g_cleared[bp * 32];
            const unsigned int target = (atomicAdd(cnt, 1u) & ~31u) + 32u;
            uint32_t it = 0;
            while (true) {
                unsigned int v;
                asm volatile("ld.acquire.gpu.global.u32 %0, [%1];" : "=r"(v) : "l"(cnt) : "memory");
                if ((int)(v - target) >= 0 || ++it > kSpinLimit) break;
                __nanosleep(200);
            }
            mbar_arrive_n(bar(kBarMbox), 1);
        }
        return;
    }
    cluster_wait();
    if (lane == 0) {
        const uint64_t pol = policy_evict_first();
        uint32_t phase = 0;
#pragma unroll 1
        for (int n = 1; n < kNumTiles; n++) {
            const int t = issue_order(n);
            const int slot = tile_slot(t);
            if (t == 30) asm volatile("prefetch.tensormap [%0];" ::"l"(&prm.wo) : "memory");
            if (t < 32) {
                mbar_wait(bar(kBarEmpty + slot), (phase >> slot) & 1);
                phase ^= 1u << slot;
            } else if (t == 32) {
#pragma unroll
                for (int i = 3; i < 7; i++) mbar_wait(bar(kBarEmpty + i), (phase >> i) & 1);
            }
            if (t >= kInFlight && t < 32) mbar_wait(bar(kBarFull + t - kInFlight), 0);
            if (t >= kLockStep0 && t < 32) {
                asm volatile("st.relaxed.cluster.shared::cluster.u32 [%0], %1;" ::"r"(mapa(sbase + kPeerOff, r ^ 1)), "r"(t) : "memory");
                uint32_t it = 0;
                int v;
                do {
                    asm volatile("ld.relaxed.cluster.shared::cta.u32 %0, [%1];" : "=r"(v) : "r"(sbase + kPeerOff) : "memory");
                } while (v < t && ++it < kSpinLimit);
            }
            if (t == 32) mbar_wait(bar(kBarFull + 31), 0);
            if (t == 33) mbar_wait(bar(kBarFull + 32), 0);
            if (t == 35) mbar_wait(bar(kBarFull + 34), 0);
            const uint32_t fb = bar(kBarFull + t), dst = sbase + slot * kSlotBytes;
            const bool split = t == 31 || t == 33 || t == 35;
            const uint32_t fb2 = t == 31 ? bar(kBarV15b) : fb;
            const uint32_t fa = t == 33 ? bar(kBarWa) : bar(kBarWa + 1);
            mbar_expect_tx(fb, split ? kHalfBytes : kSlotBytes);
            if (split) mbar_expect_tx(t == 31 ? fb2 : fa, kHalfBytes);
            if (t < 32) {
                const CUtensorMap* m = (t < 28 ? (t & 1) : (t >> 1 & 1)) ? &prm.v : &prm.k;
                const int row = kv_row0 + (t < 28 ? t >> 1 : 14 + (t & 1)) * 128;
                tma_2d_hint(dst, m, 0, row, fb, pol);
                tma_2d_hint(dst + kHalfBytes, m, 64, row, fb2, pol);
            } else {
                const int gq = t & 1, second = (t - 32) >> 1;
#pragma unroll
                for (int u = 0; u < 4; u++) {
                    const int j = gq ? (u & 1) : (u >> 1), ch = gq ? second : (u & 1), hh = gq ? (u >> 1) : second;
                    const uint32_t fw = (gq && u < 2) ? fa : fb;
                    tma_2d(sbase + tile_slot(32 + gq + 2 * j) * kSlotBytes + ch * kHalfBytes + hh * 8192, &prm.wo, 256 * r + 128 * gq + 64 * ch,
                           (head0 + j) * 128 + 64 * hh, fw);
                }
            }
        }
    }
}

typedef CUresult (*EncodeTiledFn)(CUtensorMap*, CUtensorMapDataType, cuuint32_t, void*, const cuuint64_t*, const cuuint64_t*,
                                  const cuuint32_t*, const cuuint32_t*, CUtensorMapInterleave, CUtensorMapSwizzle,
                                  CUtensorMapL2promotion, CUtensorMapFloatOOBfill);

bool make_map(EncodeTiledFn fn, CUtensorMap* m, const void* ptr, uint64_t cols, uint64_t rows, uint32_t box_cols, uint32_t box_rows) {
    cuuint64_t dims[2] = {cols, rows};
    cuuint64_t strides[1] = {cols * 2};
    cuuint32_t box[2] = {box_cols, box_rows};
    cuuint32_t es[2] = {1, 1};
    return fn(m, CU_TENSOR_MAP_DATA_TYPE_BFLOAT16, 2, const_cast<void*>(ptr), dims, strides, box, es, CU_TENSOR_MAP_INTERLEAVE_NONE,
              CU_TENSOR_MAP_SWIZZLE_128B, CU_TENSOR_MAP_L2_PROMOTION_L2_256B, CU_TENSOR_MAP_FLOAT_OOB_FILL_NONE) == CUDA_SUCCESS;
}

}

extern "C" void kernel_launch(void* const* d_in, const int* in_sizes, int n_in, void* d_out, int out_size) {
    (void)in_sizes;
    (void)n_in;
    (void)out_size;
    static EncodeTiledFn encode = nullptr;
    if (!encode) {
        void* fn = nullptr;
        cudaDriverEntryPointQueryResult qr;
        if (cudaGetDriverEntryPoint("cuTensorMapEncodeTiled", &fn, cudaEnableDefault, &qr) != cudaSuccess || !fn) return;
        encode = (EncodeTiledFn)fn;
        cudaFuncSetAttribute(fused_swa_kernel, cudaFuncAttributeMaxDynamicSharedMemorySize, (int)kSmemBytes);
    }
    Params prm;
    bool ok = make_map(encode, &prm.k, d_in[1], kDh, (uint64_t)kB * kHkv * kSk, 64, 128);
    ok = ok && make_map(encode, &prm.v, d_in[2], kDh, (uint64_t)kB * kHkv * kSk, 64, 128);
    ok = ok && make_map(encode, &prm.wo, d_in[4], kD, kHq * kDh, 64, 64);
    ok = ok && make_map(encode, &prm.wq, d_in[3], kHq * kDh, kD, 64, 128);
    ok = ok && make_map(encode, &prm.x, d_in[0], kD, kB * kSq, 64, 64);
    if (!ok) return;

    cudaLaunchConfig_t cfg = {};
    cfg.gridDim = dim3(kCtas);
    cfg.blockDim = dim3(kThreads);
    cfg.dynamicSmemBytes = kSmemBytes;
    cfg.stream = cudaStreamPerThread;
    cudaLaunchAttribute at[1];
    at[0].id = cudaLaunchAttributeClusterDimension;
    at[0].val.clusterDim.x = 2;
    at[0].val.clusterDim.y = 1;
    at[0].val.clusterDim.z = 1;
    cfg.attrs = at;
    cfg.numAttrs = 1;
    cudaLaunchKernelEx(&cfg, fused_swa_kernel, (const __nv_bfloat16*)d_in[3], (const __nv_bfloat16*)d_in[0], (__nv_bfloat16*)d_out, prm);
}
```
